```python
import torch

def _softmax(x, axis=-1):
    return torch.softmax(x, dim=axis)
def _gelu(x):
    return torch.nn.functional.gelu(x, approximate="tanh")
def _silu(x):
    return torch.nn.functional.silu(x)
def _sigmoid(x):
    return torch.sigmoid(x)
def _layernorm(x, axis=-1, eps=1e-5):
    m = x.mean(dim=axis, keepdim=True)
    v = x.var(dim=axis, keepdim=True, unbiased=False)
    return (x - m) / torch.sqrt(v + eps)
def _scatter_add(tgt, idx, src, axis=0):
    return tgt.clone().index_add_(axis, idx, src)
def _segment_sum(src, seg, n):
    out = torch.zeros((n,) + src.shape[1:], dtype=src.dtype)
    return out.index_add_(0, seg, src)
def _pad(x, pw):
    flat = tuple(v for pair in reversed(pw) for v in pair)
    return torch.nn.functional.pad(x, flat)

kernel_name = 'concat_heads__mha_block_cached__gqa_block_cached__near_ridge'

def setup_inputs():

    _w = (lambda a: (lambda t: t.to(torch.bfloat16) if t.is_floating_point() else t)(torch.as_tensor(a)))
    def _A_setup():
        B, Sq, D = 32, 32, 640
        H, Sk, Dh = 32, 32, 128
        return {
            "x": _w((lambda *s: torch.randn(*s, dtype=torch.bfloat16) * 0.8)(B, Sq, D)),
            "k_cache": _w((lambda *s: torch.randn(*s, dtype=torch.bfloat16) * 0.8)(B, H, Sk, Dh)),
            "v_cache": _w((lambda *s: torch.randn(*s, dtype=torch.bfloat16) * 0.05)(B, H, Sk, Dh)),
            "wq": _w((lambda *s: torch.randn(*s, dtype=torch.bfloat16) * 0.8)(D, H * Dh) * (D ** -0.5)),
            "wo": _w((lambda *s: torch.randn(*s, dtype=torch.bfloat16) * 0.05)(H * Dh, D) * ((H * Dh) ** -0.5)),
        }
    _A_in = _A_setup()

    def _B_setup():
        B, Sq, D = 32, 32, 640
        Hq, Hkv, Sk, Dh = 32, 32, 32, 128
        assert Hq % Hkv == 0, (Hq, Hkv)
        return {
            "x": _w((lambda *s: torch.randn(*s, dtype=torch.bfloat16) * 0.8)(B, Sq, D)),
            "k_cache": _w((lambda *s: torch.randn(*s, dtype=torch.bfloat16) * 0.8)(B, Hkv, Sk, Dh)),
            "v_cache": _w((lambda *s: torch.randn(*s, dtype=torch.bfloat16) * 0.05)(B, Hkv, Sk, Dh)),
            "wq": _w((lambda *s: torch.randn(*s, dtype=torch.bfloat16) * 0.8)(D, Hq * Dh) * (D ** -0.5)),
            "wo": _w((lambda *s: torch.randn(*s, dtype=torch.bfloat16) * 0.05)(Hq * Dh, D) * ((Hq * Dh) ** -0.5)),
        }
    _B_in = _B_setup()

    return {
        "A_x": _A_in["x"],
        "A_k_cache": _A_in["k_cache"],
        "A_v_cache": _A_in["v_cache"],
        "A_wq": _A_in["wq"],
        "A_wo": _A_in["wo"],
        "B_x": _B_in["x"],
        "B_k_cache": _B_in["k_cache"],
        "B_v_cache": _B_in["v_cache"],
        "B_wq": _B_in["wq"],
        "B_wo": _B_in["wo"],
    }

def reference(A_x, A_k_cache, A_v_cache, A_wq, A_wo, B_x, B_k_cache, B_v_cache, B_wq, B_wo):
    def _A_ref(x, k_cache, v_cache, wq, wo):
        B, Sq, D = x.shape
        H, Dh = 32, 128
        q = (lambda x, *d: x.permute(*d))((x @ wq).reshape(B, Sq, H, Dh), 0, 2, 1, 3)
        scores = torch.einsum("bhqd,bhkd->bhqk", q, k_cache) * (Dh ** -0.5)
        p = _softmax(scores, axis=-1)
        o = torch.einsum("bhqk,bhkd->bhqd", p, v_cache)
        return (lambda x, *d: x.permute(*d))(o, 0, 2, 1, 3).reshape(B, Sq, H * Dh) @ wo

    def _B_ref(x, k_cache, v_cache, wq, wo):
        B, Sq, D = x.shape
        Hq, Dh = 32, 128
        Hkv = k_cache.shape[1]
        rep = Hq // Hkv
        q = (lambda x, *d: x.permute(*d))((x @ wq).reshape(B, Sq, Hq, Dh), 0, 2, 1, 3)
        k = (lambda x, n, axis: torch.repeat_interleave(x, n, dim=axis))(k_cache, rep, axis=1)
        v = (lambda x, n, axis: torch.repeat_interleave(x, n, dim=axis))(v_cache, rep, axis=1)
        scores = torch.einsum("bhqd,bhkd->bhqk", q, k) * (Dh ** -0.5)
        p = _softmax(scores, axis=-1)
        o = torch.einsum("bhqk,bhkd->bhqd", p, v)
        return (lambda x, *d: x.permute(*d))(o, 0, 2, 1, 3).reshape(B, Sq, Hq * Dh) @ wo

    a = _A_ref(A_x, A_k_cache, A_v_cache, A_wq, A_wo)
    b = _B_ref(B_x, B_k_cache, B_v_cache, B_wq, B_wo)
    return torch.concatenate([a, b], axis=-1)
```

```cpp
#include <cuda_runtime.h>
#include <cuda_bf16.h>
#include <cuda.h>
#include <stdint.h>

namespace {

constexpr int SLOT = 16384;
constexpr int NSLOT = 14;
constexpr int NR = 10;
constexpr uint32_t SD = SLOT >> 4;
constexpr int SMEM_BYTES = NSLOT * SLOT + 3072;

#define PF_NS 352
#define PF0 800
#define EPB 780
#define EPD 390
#define LATE0 200

struct alignas(64) Params {
    CUtensorMap x[2], wq[2], k[2], v[2], wo[2], out;
    const __nv_bfloat16* kptr[2];
    const __nv_bfloat16* vptr[2];
    const __nv_bfloat16* xw[4];
    __nv_bfloat16* optr;
    int zero_in_kernel;
};

__device__ unsigned int g_zero_cnt[16];
__device__ unsigned int g_sink;

__device__ __forceinline__ uint32_t gtime32() { uint32_t t; asm volatile("mov.u32 %0, %%globaltimer_lo;" : "=r"(t)); return t; }
__device__ __forceinline__ uint32_t clk32() { uint32_t t; asm volatile("mov.u32 %0, %%clock;" : "=r"(t)); return t; }
__device__ __forceinline__ bool elect_one() {
    uint32_t pred;
    asm volatile("{\n.reg .pred p;\nelect.sync _|p, 0xffffffff;\nselp.u32 %0, 1, 0, p;\n}" : "=r"(pred));
    return pred != 0;
}
__device__ __forceinline__ uint32_t smem_u32(const void* p) { return (uint32_t)__cvta_generic_to_shared(p); }
__device__ __forceinline__ void mbar_init(uint32_t bar, uint32_t cnt) { asm volatile("mbarrier.init.shared::cta.b64 [%0], %1;" :: "r"(bar), "r"(cnt) : "memory"); }
__device__ __forceinline__ void mbar_expect_tx(uint32_t bar, uint32_t bytes) { asm volatile("mbarrier.arrive.expect_tx.shared::cta.b64 _, [%0], %1;" :: "r"(bar), "r"(bytes) : "memory"); }
__device__ __forceinline__ void mbar_arrive_cluster(uint32_t remote_bar) { asm volatile("mbarrier.arrive.shared::cluster.b64 _, [%0];" :: "r"(remote_bar) : "memory"); }
__device__ __forceinline__ void mbar_arrive_local(uint32_t bar) { asm volatile("mbarrier.arrive.shared::cta.b64 _, [%0];" :: "r"(bar) : "memory"); }
__device__ __forceinline__ uint32_t mapa(uint32_t addr, uint32_t cta) { uint32_t r; asm volatile("mapa.shared::cluster.u32 %0, %1, %2;" : "=r"(r) : "r"(addr), "r"(cta)); return r; }
__device__ __forceinline__ void mbar_wait(uint32_t bar, uint32_t parity) {
#pragma unroll 1
    for (uint32_t it = 0; it < (1u << 24); it++) {
        uint32_t ok;
        asm volatile("{\n.reg .pred p;\nmbarrier.try_wait.parity.shared::cta.b64 p, [%1], %2;\nselp.u32 %0, 1, 0, p;\n}" : "=r"(ok) : "r"(bar), "r"(parity) : "memory");
        if (ok) break;
    }
}
__device__ __forceinline__ void mbar_wait2(uint32_t b0, uint32_t p0, uint32_t b1, uint32_t p1) {
#pragma unroll 1
    for (uint32_t it = 0; it < (1u << 24); it++) {
        uint32_t ok;
        asm volatile("{\n.reg .pred p, q;\nmbarrier.try_wait.parity.shared::cta.b64 p, [%1], %2;\nmbarrier.try_wait.parity.shared::cta.b64 q, [%3], %4;\n"
                     "and.pred p, p, q;\nselp.u32 %0, 1, 0, p;\n}" : "=r"(ok) : "r"(b0), "r"(p0), "r"(b1), "r"(p1) : "memory");
        if (ok) break;
    }
}
__device__ __forceinline__ void mbar_wait4(uint32_t b0, uint32_t p0, uint32_t b1, uint32_t p1, uint32_t b2, uint32_t p2, uint32_t b3, uint32_t p3) {
#pragma unroll 1
    for (uint32_t it = 0; it < (1u << 24); it++) {
        uint32_t ok;
        asm volatile("{\n.reg .pred p, q, r, s;\nmbarrier.try_wait.parity.shared::cta.b64 p, [%1], %2;\nmbarrier.try_wait.parity.shared::cta.b64 q, [%3], %4;\n"
                     "mbarrier.try_wait.parity.shared::cta.b64 r, [%5], %6;\nmbarrier.try_wait.parity.shared::cta.b64 s, [%7], %8;\n"
                     "and.pred p, p, q;\nand.pred r, r, s;\nand.pred p, p, r;\nselp.u32 %0, 1, 0, p;\n}"
                     : "=r"(ok) : "r"(b0), "r"(p0), "r"(b1), "r"(p1), "r"(b2), "r"(p2), "r"(b3), "r"(p3) : "memory");
        if (ok) break;
    }
}
__device__ __forceinline__ void tma2d(uint32_t dst, const CUtensorMap* m, uint32_t bar, int c0, int c1) {
    asm volatile("cp.async.bulk.tensor.2d.shared::cluster.global.mbarrier::complete_tx::bytes [%0], [%1, {%3, %4}], [%2];"
        :: "r"(dst), "l"(m), "r"(bar), "r"(c0), "r"(c1) : "memory");
}
__device__ __forceinline__ void tma2d_mc(uint32_t dst, const CUtensorMap* m, uint32_t bar, int c0, int c1) {
    asm volatile("cp.async.bulk.tensor.2d.shared::cluster.global.mbarrier::complete_tx::bytes.multicast::cluster [%0], [%1, {%3, %4}], [%2], %5;"
        :: "r"(dst), "l"(m), "r"(bar), "r"(c0), "r"(c1), "h"((uint16_t)3) : "memory");
}
__device__ __forceinline__ void tma3d(uint32_t dst, const CUtensorMap* m, uint32_t bar, int c0, int c1, int c2, uint64_t pol) {
    asm volatile("cp.async.bulk.tensor.3d.shared::cluster.global.mbarrier::complete_tx::bytes.L2::cache_hint [%0], [%1, {%3, %4, %5}], [%2], %6;"
        :: "r"(dst), "l"(m), "r"(bar), "r"(c0), "r"(c1), "r"(c2), "l"(pol) : "memory");
}
__device__ __forceinline__ void tma5d(uint32_t dst, const CUtensorMap* m, uint32_t bar, int c0, int c1, int c2, int c3, int c4, uint64_t pol) {
    asm volatile("cp.async.bulk.tensor.5d.shared::cluster.global.mbarrier::complete_tx::bytes.L2::cache_hint [%0], [%1, {%3, %4, %5, %6, %7}], [%2], %8;"
        :: "r"(dst), "l"(m), "r"(bar), "r"(c0), "r"(c1), "r"(c2), "r"(c3), "r"(c4), "l"(pol) : "memory");
}
__device__ __forceinline__ void tma_red2d_commit(bool pred, const CUtensorMap* m, uint32_t src, int c0, int c1) {
    asm volatile("{\n.reg .pred p;\nsetp.ne.u32 p, %4, 0;\n"
        "@p cp.reduce.async.bulk.tensor.2d.global.shared::cta.add.tile.bulk_group [%0, {%2, %3}], [%1];\n"
        "@p cp.async.bulk.commit_group;\n}"
        :: "l"(m), "r"(src), "r"(c0), "r"(c1), "r"((uint32_t)pred) : "memory");
}
__device__ __forceinline__ void pf2d(const CUtensorMap* m, int c0, int c1) {
    asm volatile("cp.async.bulk.prefetch.tensor.2d.L2.global.tile [%0, {%1, %2}];" :: "l"(m), "r"(c0), "r"(c1) : "memory");
}
__device__ __forceinline__ void pf1d(const void* p, uint32_t bytes) {
    asm volatile("cp.async.bulk.prefetch.L2.global [%0], %1;" :: "l"(p), "r"(bytes) : "memory");
}
__device__ __forceinline__ uint32_t ld_pf128(const void* a) { uint32_t v; asm volatile("ld.global.cg.L2::128B.u32 %0, [%1];" : "=r"(v) : "l"(a) : "memory"); return v; }
__device__ __forceinline__ uint32_t ld_pf256(const void* a) { uint32_t v; asm volatile("ld.global.cg.L2::256B.u32 %0, [%1];" : "=r"(v) : "l"(a) : "memory"); return v; }
__device__ __forceinline__ void ldsm4(uint32_t addr, uint32_t& a, uint32_t& b, uint32_t& c, uint32_t& d) {
    asm volatile("ldmatrix.sync.aligned.m8n8.x4.shared.b16 {%0, %1, %2, %3}, [%4];" : "=r"(a), "=r"(b), "=r"(c), "=r"(d) : "r"(addr) : "memory");
}
__device__ __forceinline__ void stsm4(uint32_t addr, uint32_t a, uint32_t b, uint32_t c, uint32_t d) {
    asm volatile("stmatrix.sync.aligned.m8n8.x4.shared.b16 [%0], {%1, %2, %3, %4};" :: "r"(addr), "r"(a), "r"(b), "r"(c), "r"(d) : "memory");
}
__device__ __forceinline__ uint32_t pack_bf16(float lo, float hi) {
    uint32_t r; asm volatile("cvt.rn.bf16x2.f32 %0, %1, %2;" : "=r"(r) : "f"(hi), "f"(lo)); return r;
}
__device__ __forceinline__ float ex2(float x) { float r; asm("ex2.approx.ftz.f32 %0, %1;" : "=f"(r) : "f"(x)); return r; }
__device__ __forceinline__ uint32_t mkdesc(uint32_t addr, uint32_t lbo) { return ((addr & 0x3FFFFu) >> 4) | ((lbo >> 4) << 16); }
__device__ __forceinline__ void sched_fence() {
    asm volatile("{\n.reg .pred p;\nsetp.ne.u32 p, %0, 0;\nSF_%=:\nvote.sync.any.pred p, p, 0xffffffff;\n@p bra SF_%=;\n}" :: "r"(blockIdx.y) : "memory");
}
#define WG_FENCE() asm volatile("wgmma.fence.sync.aligned;" ::: "memory")
#define WG_COMMIT() asm volatile("wgmma.commit_group.sync.aligned;" ::: "memory")
#define WG_WAIT(n) asm volatile("wgmma.wait_group.sync.aligned %0;" :: "n"(n) : "memory")
template <int N> __device__ __forceinline__ void pin(float (&d)[N]) {
#pragma unroll
    for (int i = 0; i < N; i++) asm volatile("" : "+f"(d[i]) :: "memory");
}

template <int DN> __device__ __forceinline__ void wgmma_n128_ss_t1(float (&d)[DN], uint32_t da, uint32_t db, bool accum) {
    if (accum) {
        asm volatile("{\n.reg .b64 da, db;\nmov.b64 da, {%64, 0x40000040};\nmov.b64 db, {%65, 0x40000040};\n"
            "wgmma.mma_async.sync.aligned.m64n128k16.f32.bf16.bf16 {"
            "%0, %1, %2, %3, %4, %5, %6, %7, %8, %9, %10, %11, %12, %13, %14, %15, "
            "%16, %17, %18, %19, %20, %21, %22, %23, %24, %25, %26, %27, %28, %29, %30, %31, "
            "%32, %33, %34, %35, %36, %37, %38, %39, %40, %41, %42, %43, %44, %45, %46, %47, "
            "%48, %49, %50, %51, %52, %53, %54, %55, %56, %57, %58, %59, %60, %61, %62, %63}, "
            "da, db, 1, 1, 1, 0, 1;\n}"
            : "+f"(d[0]), "+f"(d[1]), "+f"(d[2]), "+f"(d[3]), "+f"(d[4]), "+f"(d[5]), "+f"(d[6]), "+f"(d[7]),
              "+f"(d[8]), "+f"(d[9]), "+f"(d[10]), "+f"(d[11]), "+f"(d[12]), "+f"(d[13]), "+f"(d[14]), "+f"(d[15]),
              "+f"(d[16]), "+f"(d[17]), "+f"(d[18]), "+f"(d[19]), "+f"(d[20]), "+f"(d[21]), "+f"(d[22]), "+f"(d[23]),
              "+f"(d[24]), "+f"(d[25]), "+f"(d[26]), "+f"(d[27]), "+f"(d[28]), "+f"(d[29]), "+f"(d[30]), "+f"(d[31]),
              "+f"(d[32]), "+f"(d[33]), "+f"(d[34]), "+f"(d[35]), "+f"(d[36]), "+f"(d[37]), "+f"(d[38]), "+f"(d[39]),
              "+f"(d[40]), "+f"(d[41]), "+f"(d[42]), "+f"(d[43]), "+f"(d[44]), "+f"(d[45]), "+f"(d[46]), "+f"(d[47]),
              "+f"(d[48]), "+f"(d[49]), "+f"(d[50]), "+f"(d[51]), "+f"(d[52]), "+f"(d[53]), "+f"(d[54]), "+f"(d[55]),
              "+f"(d[56]), "+f"(d[57]), "+f"(d[58]), "+f"(d[59]), "+f"(d[60]), "+f"(d[61]), "+f"(d[62]), "+f"(d[63])
            : "r"(da), "r"(db));
    } else {
        asm volatile("{\n.reg .b64 da, db;\nmov.b64 da, {%64, 0x40000040};\nmov.b64 db, {%65, 0x40000040};\n"
            "wgmma.mma_async.sync.aligned.m64n128k16.f32.bf16.bf16 {"
            "%0, %1, %2, %3, %4, %5, %6, %7, %8, %9, %10, %11, %12, %13, %14, %15, "
            "%16, %17, %18, %19, %20, %21, %22, %23, %24, %25, %26, %27, %28, %29, %30, %31, "
            "%32, %33, %34, %35, %36, %37, %38, %39, %40, %41, %42, %43, %44, %45, %46, %47, "
            "%48, %49, %50, %51, %52, %53, %54, %55, %56, %57, %58, %59, %60, %61, %62, %63}, "
            "da, db, 0, 1, 1, 0, 1;\n}"
            : "+f"(d[0]), "+f"(d[1]), "+f"(d[2]), "+f"(d[3]), "+f"(d[4]), "+f"(d[5]), "+f"(d[6]), "+f"(d[7]),
              "+f"(d[8]), "+f"(d[9]), "+f"(d[10]), "+f"(d[11]), "+f"(d[12]), "+f"(d[13]), "+f"(d[14]), "+f"(d[15]),
              "+f"(d[16]), "+f"(d[17]), "+f"(d[18]), "+f"(d[19]), "+f"(d[20]), "+f"(d[21]), "+f"(d[22]), "+f"(d[23]),
              "+f"(d[24]), "+f"(d[25]), "+f"(d[26]), "+f"(d[27]), "+f"(d[28]), "+f"(d[29]), "+f"(d[30]), "+f"(d[31]),
              "+f"(d[32]), "+f"(d[33]), "+f"(d[34]), "+f"(d[35]), "+f"(d[36]), "+f"(d[37]), "+f"(d[38]), "+f"(d[39]),
              "+f"(d[40]), "+f"(d[41]), "+f"(d[42]), "+f"(d[43]), "+f"(d[44]), "+f"(d[45]), "+f"(d[46]), "+f"(d[47]),
              "+f"(d[48]), "+f"(d[49]), "+f"(d[50]), "+f"(d[51]), "+f"(d[52]), "+f"(d[53]), "+f"(d[54]), "+f"(d[55]),
              "+f"(d[56]), "+f"(d[57]), "+f"(d[58]), "+f"(d[59]), "+f"(d[60]), "+f"(d[61]), "+f"(d[62]), "+f"(d[63])
            : "r"(da), "r"(db));
    }
}
template <int DN> __device__ __forceinline__ void wgmma_n128_rs_t1(float (&d)[DN], uint32_t a0, uint32_t a1, uint32_t a2, uint32_t a3, uint32_t db, bool accum) {
    if (accum) {
        asm volatile("{\n.reg .b64 da, db;\nmov.b64 db, {%68, 0x40000040};\n"
            "wgmma.mma_async.sync.aligned.m64n128k16.f32.bf16.bf16 {"
            "%0, %1, %2, %3, %4, %5, %6, %7, %8, %9, %10, %11, %12, %13, %14, %15, "
            "%16, %17, %18, %19, %20, %21, %22, %23, %24, %25, %26, %27, %28, %29, %30, %31, "
            "%32, %33, %34, %35, %36, %37, %38, %39, %40, %41, %42, %43, %44, %45, %46, %47, "
            "%48, %49, %50, %51, %52, %53, %54, %55, %56, %57, %58, %59, %60, %61, %62, %63}, "
            "{%64, %65, %66, %67}, db, 1, 1, 1, 1;\n}"
            : "+f"(d[0]), "+f"(d[1]), "+f"(d[2]), "+f"(d[3]), "+f"(d[4]), "+f"(d[5]), "+f"(d[6]), "+f"(d[7]),
              "+f"(d[8]), "+f"(d[9]), "+f"(d[10]), "+f"(d[11]), "+f"(d[12]), "+f"(d[13]), "+f"(d[14]), "+f"(d[15]),
              "+f"(d[16]), "+f"(d[17]), "+f"(d[18]), "+f"(d[19]), "+f"(d[20]), "+f"(d[21]), "+f"(d[22]), "+f"(d[23]),
              "+f"(d[24]), "+f"(d[25]), "+f"(d[26]), "+f"(d[27]), "+f"(d[28]), "+f"(d[29]), "+f"(d[30]), "+f"(d[31]),
              "+f"(d[32]), "+f"(d[33]), "+f"(d[34]), "+f"(d[35]), "+f"(d[36]), "+f"(d[37]), "+f"(d[38]), "+f"(d[39]),
              "+f"(d[40]), "+f"(d[41]), "+f"(d[42]), "+f"(d[43]), "+f"(d[44]), "+f"(d[45]), "+f"(d[46]), "+f"(d[47]),
              "+f"(d[48]), "+f"(d[49]), "+f"(d[50]), "+f"(d[51]), "+f"(d[52]), "+f"(d[53]), "+f"(d[54]), "+f"(d[55]),
              "+f"(d[56]), "+f"(d[57]), "+f"(d[58]), "+f"(d[59]), "+f"(d[60]), "+f"(d[61]), "+f"(d[62]), "+f"(d[63])
            : "r"(a0), "r"(a1), "r"(a2), "r"(a3), "r"(db));
    } else {
        asm volatile("{\n.reg .b64 da, db;\nmov.b64 db, {%68, 0x40000040};\n"
            "wgmma.mma_async.sync.aligned.m64n128k16.f32.bf16.bf16 {"
            "%0, %1, %2, %3, %4, %5, %6, %7, %8, %9, %10, %11, %12, %13, %14, %15, "
            "%16, %17, %18, %19, %20, %21, %22, %23, %24, %25, %26, %27, %28, %29, %30, %31, "
            "%32, %33, %34, %35, %36, %37, %38, %39, %40, %41, %42, %43, %44, %45, %46, %47, "
            "%48, %49, %50, %51, %52, %53, %54, %55, %56, %57, %58, %59, %60, %61, %62, %63}, "
            "{%64, %65, %66, %67}, db, 0, 1, 1, 1;\n}"
            : "+f"(d[0]), "+f"(d[1]), "+f"(d[2]), "+f"(d[3]), "+f"(d[4]), "+f"(d[5]), "+f"(d[6]), "+f"(d[7]),
              "+f"(d[8]), "+f"(d[9]), "+f"(d[10]), "+f"(d[11]), "+f"(d[12]), "+f"(d[13]), "+f"(d[14]), "+f"(d[15]),
              "+f"(d[16]), "+f"(d[17]), "+f"(d[18]), "+f"(d[19]), "+f"(d[20]), "+f"(d[21]), "+f"(d[22]), "+f"(d[23]),
              "+f"(d[24]), "+f"(d[25]), "+f"(d[26]), "+f"(d[27]), "+f"(d[28]), "+f"(d[29]), "+f"(d[30]), "+f"(d[31]),
              "+f"(d[32]), "+f"(d[33]), "+f"(d[34]), "+f"(d[35]), "+f"(d[36]), "+f"(d[37]), "+f"(d[38]), "+f"(d[39]),
              "+f"(d[40]), "+f"(d[41]), "+f"(d[42]), "+f"(d[43]), "+f"(d[44]), "+f"(d[45]), "+f"(d[46]), "+f"(d[47]),
              "+f"(d[48]), "+f"(d[49]), "+f"(d[50]), "+f"(d[51]), "+f"(d[52]), "+f"(d[53]), "+f"(d[54]), "+f"(d[55]),
              "+f"(d[56]), "+f"(d[57]), "+f"(d[58]), "+f"(d[59]), "+f"(d[60]), "+f"(d[61]), "+f"(d[62]), "+f"(d[63])
            : "r"(a0), "r"(a1), "r"(a2), "r"(a3), "r"(db));
    }
}
template <int DN> __device__ __forceinline__ void wgmma_n64_rs_t0(float (&d)[DN], uint32_t a0, uint32_t a1, uint32_t a2, uint32_t a3, uint32_t db, bool accum) {
    if (accum) {
        asm volatile("{\n.reg .b64 da, db;\nmov.b64 db, {%36, 0x40000040};\n"
            "wgmma.mma_async.sync.aligned.m64n64k16.f32.bf16.bf16 {"
            "%0, %1, %2, %3, %4, %5, %6, %7, %8, %9, %10, %11, %12, %13, %14, %15, "
            "%16, %17, %18, %19, %20, %21, %22, %23, %24, %25, %26, %27, %28, %29, %30, %31}, "
            "{%32, %33, %34, %35}, db, 1, 1, 1, 0;\n}"
            : "+f"(d[0]), "+f"(d[1]), "+f"(d[2]), "+f"(d[3]), "+f"(d[4]), "+f"(d[5]), "+f"(d[6]), "+f"(d[7]),
              "+f"(d[8]), "+f"(d[9]), "+f"(d[10]), "+f"(d[11]), "+f"(d[12]), "+f"(d[13]), "+f"(d[14]), "+f"(d[15]),
              "+f"(d[16]), "+f"(d[17]), "+f"(d[18]), "+f"(d[19]), "+f"(d[20]), "+f"(d[21]), "+f"(d[22]), "+f"(d[23]),
              "+f"(d[24]), "+f"(d[25]), "+f"(d[26]), "+f"(d[27]), "+f"(d[28]), "+f"(d[29]), "+f"(d[30]), "+f"(d[31])
            : "r"(a0), "r"(a1), "r"(a2), "r"(a3), "r"(db));
    } else {
        asm volatile("{\n.reg .b64 da, db;\nmov.b64 db, {%36, 0x40000040};\n"
            "wgmma.mma_async.sync.aligned.m64n64k16.f32.bf16.bf16 {"
            "%0, %1, %2, %3, %4, %5, %6, %7, %8, %9, %10, %11, %12, %13, %14, %15, "
            "%16, %17, %18, %19, %20, %21, %22, %23, %24, %25, %26, %27, %28, %29, %30, %31}, "
            "{%32, %33, %34, %35}, db, 0, 1, 1, 0;\n}"
            : "+f"(d[0]), "+f"(d[1]), "+f"(d[2]), "+f"(d[3]), "+f"(d[4]), "+f"(d[5]), "+f"(d[6]), "+f"(d[7]),
              "+f"(d[8]), "+f"(d[9]), "+f"(d[10]), "+f"(d[11]), "+f"(d[12]), "+f"(d[13]), "+f"(d[14]), "+f"(d[15]),
              "+f"(d[16]), "+f"(d[17]), "+f"(d[18]), "+f"(d[19]), "+f"(d[20]), "+f"(d[21]), "+f"(d[22]), "+f"(d[23]),
              "+f"(d[24]), "+f"(d[25]), "+f"(d[26]), "+f"(d[27]), "+f"(d[28]), "+f"(d[29]), "+f"(d[30]), "+f"(d[31])
            : "r"(a0), "r"(a1), "r"(a2), "r"(a3), "r"(db));
    }
}
template <int DN> __device__ __forceinline__ void wgmma_n128_sp_t1(float (&d)[DN], uint32_t a0, uint32_t a1, uint32_t a2, uint32_t a3, uint32_t db, uint32_t meta, bool accum) {
    if (accum) {
        asm volatile("{\n.reg .b64 da, db;\nmov.b64 db, {%68, 0x40000040};\n"
            "wgmma.mma_async.sp.sync.aligned.m64n128k32.f32.bf16.bf16 {"
            "%0, %1, %2, %3, %4, %5, %6, %7, %8, %9, %10, %11, %12, %13, %14, %15, "
            "%16, %17, %18, %19, %20, %21, %22, %23, %24, %25, %26, %27, %28, %29, %30, %31, "
            "%32, %33, %34, %35, %36, %37, %38, %39, %40, %41, %42, %43, %44, %45, %46, %47, "
            "%48, %49, %50, %51, %52, %53, %54, %55, %56, %57, %58, %59, %60, %61, %62, %63}, "
            "{%64, %65, %66, %67}, db, %69, 0, 1, 1, 1, 1;\n}"
            : "+f"(d[0]), "+f"(d[1]), "+f"(d[2]), "+f"(d[3]), "+f"(d[4]), "+f"(d[5]), "+f"(d[6]), "+f"(d[7]),
              "+f"(d[8]), "+f"(d[9]), "+f"(d[10]), "+f"(d[11]), "+f"(d[12]), "+f"(d[13]), "+f"(d[14]), "+f"(d[15]),
              "+f"(d[16]), "+f"(d[17]), "+f"(d[18]), "+f"(d[19]), "+f"(d[20]), "+f"(d[21]), "+f"(d[22]), "+f"(d[23]),
              "+f"(d[24]), "+f"(d[25]), "+f"(d[26]), "+f"(d[27]), "+f"(d[28]), "+f"(d[29]), "+f"(d[30]), "+f"(d[31]),
              "+f"(d[32]), "+f"(d[33]), "+f"(d[34]), "+f"(d[35]), "+f"(d[36]), "+f"(d[37]), "+f"(d[38]), "+f"(d[39]),
              "+f"(d[40]), "+f"(d[41]), "+f"(d[42]), "+f"(d[43]), "+f"(d[44]), "+f"(d[45]), "+f"(d[46]), "+f"(d[47]),
              "+f"(d[48]), "+f"(d[49]), "+f"(d[50]), "+f"(d[51]), "+f"(d[52]), "+f"(d[53]), "+f"(d[54]), "+f"(d[55]),
              "+f"(d[56]), "+f"(d[57]), "+f"(d[58]), "+f"(d[59]), "+f"(d[60]), "+f"(d[61]), "+f"(d[62]), "+f"(d[63])
            : "r"(a0), "r"(a1), "r"(a2), "r"(a3), "r"(db), "r"(meta));
    } else {
        asm volatile("{\n.reg .b64 da, db;\nmov.b64 db, {%68, 0x40000040};\n"
            "wgmma.mma_async.sp.sync.aligned.m64n128k32.f32.bf16.bf16 {"
            "%0, %1, %2, %3, %4, %5, %6, %7, %8, %9, %10, %11, %12, %13, %14, %15, "
            "%16, %17, %18, %19, %20, %21, %22, %23, %24, %25, %26, %27, %28, %29, %30, %31, "
            "%32, %33, %34, %35, %36, %37, %38, %39, %40, %41, %42, %43, %44, %45, %46, %47, "
            "%48, %49, %50, %51, %52, %53, %54, %55, %56, %57, %58, %59, %60, %61, %62, %63}, "
            "{%64, %65, %66, %67}, db, %69, 0, 0, 1, 1, 1;\n}"
            : "+f"(d[0]), "+f"(d[1]), "+f"(d[2]), "+f"(d[3]), "+f"(d[4]), "+f"(d[5]), "+f"(d[6]), "+f"(d[7]),
              "+f"(d[8]), "+f"(d[9]), "+f"(d[10]), "+f"(d[11]), "+f"(d[12]), "+f"(d[13]), "+f"(d[14]), "+f"(d[15]),
              "+f"(d[16]), "+f"(d[17]), "+f"(d[18]), "+f"(d[19]), "+f"(d[20]), "+f"(d[21]), "+f"(d[22]), "+f"(d[23]),
              "+f"(d[24]), "+f"(d[25]), "+f"(d[26]), "+f"(d[27]), "+f"(d[28]), "+f"(d[29]), "+f"(d[30]), "+f"(d[31]),
              "+f"(d[32]), "+f"(d[33]), "+f"(d[34]), "+f"(d[35]), "+f"(d[36]), "+f"(d[37]), "+f"(d[38]), "+f"(d[39]),
              "+f"(d[40]), "+f"(d[41]), "+f"(d[42]), "+f"(d[43]), "+f"(d[44]), "+f"(d[45]), "+f"(d[46]), "+f"(d[47]),
              "+f"(d[48]), "+f"(d[49]), "+f"(d[50]), "+f"(d[51]), "+f"(d[52]), "+f"(d[53]), "+f"(d[54]), "+f"(d[55]),
              "+f"(d[56]), "+f"(d[57]), "+f"(d[58]), "+f"(d[59]), "+f"(d[60]), "+f"(d[61]), "+f"(d[62]), "+f"(d[63])
            : "r"(a0), "r"(a1), "r"(a2), "r"(a3), "r"(db), "r"(meta));
    }
}
template <int DN> __device__ __forceinline__ void wgmma_n64_rs_t1(float (&d)[DN], uint32_t a0, uint32_t a1, uint32_t a2, uint32_t a3, uint32_t db, bool accum) {
    if (accum) {
        asm volatile("{\n.reg .b64 da, db;\nmov.b64 db, {%36, 0x40000040};\n"
            "wgmma.mma_async.sync.aligned.m64n64k16.f32.bf16.bf16 {"
            "%0, %1, %2, %3, %4, %5, %6, %7, %8, %9, %10, %11, %12, %13, %14, %15, "
            "%16, %17, %18, %19, %20, %21, %22, %23, %24, %25, %26, %27, %28, %29, %30, %31}, "
            "{%32, %33, %34, %35}, db, 1, 1, 1, 1;\n}"
            : "+f"(d[0]), "+f"(d[1]), "+f"(d[2]), "+f"(d[3]), "+f"(d[4]), "+f"(d[5]), "+f"(d[6]), "+f"(d[7]),
              "+f"(d[8]), "+f"(d[9]), "+f"(d[10]), "+f"(d[11]), "+f"(d[12]), "+f"(d[13]), "+f"(d[14]), "+f"(d[15]),
              "+f"(d[16]), "+f"(d[17]), "+f"(d[18]), "+f"(d[19]), "+f"(d[20]), "+f"(d[21]), "+f"(d[22]), "+f"(d[23]),
              "+f"(d[24]), "+f"(d[25]), "+f"(d[26]), "+f"(d[27]), "+f"(d[28]), "+f"(d[29]), "+f"(d[30]), "+f"(d[31])
            : "r"(a0), "r"(a1), "r"(a2), "r"(a3), "r"(db));
    } else {
        asm volatile("{\n.reg .b64 da, db;\nmov.b64 db, {%36, 0x40000040};\n"
            "wgmma.mma_async.sync.aligned.m64n64k16.f32.bf16.bf16 {"
            "%0, %1, %2, %3, %4, %5, %6, %7, %8, %9, %10, %11, %12, %13, %14, %15, "
            "%16, %17, %18, %19, %20, %21, %22, %23, %24, %25, %26, %27, %28, %29, %30, %31}, "
            "{%32, %33, %34, %35}, db, 0, 1, 1, 1;\n}"
            : "+f"(d[0]), "+f"(d[1]), "+f"(d[2]), "+f"(d[3]), "+f"(d[4]), "+f"(d[5]), "+f"(d[6]), "+f"(d[7]),
              "+f"(d[8]), "+f"(d[9]), "+f"(d[10]), "+f"(d[11]), "+f"(d[12]), "+f"(d[13]), "+f"(d[14]), "+f"(d[15]),
              "+f"(d[16]), "+f"(d[17]), "+f"(d[18]), "+f"(d[19]), "+f"(d[20]), "+f"(d[21]), "+f"(d[22]), "+f"(d[23]),
              "+f"(d[24]), "+f"(d[25]), "+f"(d[26]), "+f"(d[27]), "+f"(d[28]), "+f"(d[29]), "+f"(d[30]), "+f"(d[31])
            : "r"(a0), "r"(a1), "r"(a2), "r"(a3), "r"(db));
    }
}

__global__ void __cluster_dims__(2, 1, 1) __launch_bounds__(384, 1)
fused_kernel(const __grid_constant__ Params prm) {
    extern __shared__ __align__(1024) uint8_t smem_raw[];
    const uint32_t sb = (smem_u32(smem_raw) + 1023u) & ~1023u;
    const uint32_t fullb = sb + NSLOT * SLOT;
    const uint32_t emptyb = fullb + NSLOT * 8;
    const uint32_t zerob = emptyb + NSLOT * 8;
    const uint32_t gob = zerob + 8;
    const int tid = threadIdx.x, warp = __shfl_sync(0xffffffffu, tid >> 5, 0), lane = tid & 31;
    const uint32_t rank = blockIdx.x & 1;
    const int cid = blockIdx.x >> 1;
    int grp, mem;
    if (cid < 4) { grp = 1; mem = cid; }
    else if (cid < 36) { grp = ((cid - 4) & 7) * 2; mem = (cid - 4) >> 3; }
    else { mem = ((cid - 36) * 37) >> 8; grp = (cid - 36 - mem * 7) * 2 + 3; }
    const int p = grp >> 3, g = grp & 7, mt = (mem << 1) | (int)rank;

    uint32_t t_entry = 0;
    const char* early = nullptr;
    if (warp == 8) {
        if (elect_one()) {
            mbar_init(fullb + 10 * 8, 1); mbar_init(fullb, 1); mbar_init(fullb + 11 * 8, 1); mbar_init(fullb + 8, 1);
            asm volatile("fence.mbarrier_init.release.cluster;" ::: "memory");
#pragma unroll
            for (int j = 0; j < 2; j++) {
                mbar_expect_tx(fullb + (10 + j) * 8, SLOT);
                tma2d(sb + (10 + j) * SLOT, &prm.x[p], fullb + (10 + j) * 8, j * 64, mt * 128);
                mbar_expect_tx(fullb + j * 8, SLOT);
                tma2d(sb + j * SLOT, &prm.wq[p], fullb + j * 8, g * 512, j * 64);
                tma2d(sb + j * SLOT + 8192, &prm.wq[p], fullb + j * 8, g * 512 + 64, j * 64);
            }
        }
    } else {
        if (warp < 8) {
            t_entry = clk32();
            const bool isx = warp < 4;
            const uint32_t row = isx ? mt * 128 + g * 16 + (lane >> 1) : (warp & 3) * 128 + (lane >> 4) * 64 + mt * 8 + ((lane & 15) >> 1);
            early = (const char*)prm.xw[isx ? p : 2 + p] + (size_t)row * (isx ? 1280 : 8192) + (isx ? warp * 256 : g * 1024) + (lane & 1) * 128;
            if ((warp & 3) == 0) asm volatile("prefetch.global.L2 [%0];" :: "l"(early) : "memory");
        }
        if (lane == 0) {
            const int b0 = warp < 8 ? 2 + warp : (warp == 9 ? 12 : (warp == 10 ? 13 : 28));
            mbar_init(fullb + b0 * 8, 1);
            if (warp != 11) mbar_init(fullb + (warp < 8 ? 14 + warp : 13 + warp) * 8, 4);
            else mbar_init(gob, 1);
            if (warp < 4) mbar_init(fullb + (24 + warp) * 8, 2);
            asm volatile("fence.mbarrier_init.release.cluster;" ::: "memory");
        }
    }
    __syncwarp();
    asm volatile("barrier.cluster.arrive.relaxed.aligned;" ::: "memory");
    if (warp < 8 && (warp & 3) != 0) {
        const uint32_t tl = t_entry + EPB + ((warp & 3) - 1) * EPD;
        while ((int)(clk32() - tl) < 0) {}
        asm volatile("prefetch.global.L2 [%0];" :: "l"(early) : "memory");
    }

    if (warp >= 8) {
        asm volatile("setmaxnreg.dec.sync.aligned.u32 24;");
        if (warp == 8) {
            const CUtensorMap* mx = &prm.x[p];
            const CUtensorMap* mwq = &prm.wq[p];
            const CUtensorMap* mk = &prm.k[p];
            const CUtensorMap* mv = &prm.v[p];
            const CUtensorMap* mwo = &prm.wo[p];
            asm volatile("barrier.cluster.wait.aligned;" ::: "memory");
            if (elect_one()) {
#pragma unroll
                for (int j = 2; j < 4; j++) {
                    mbar_expect_tx(fullb + (10 + j) * 8, SLOT);
                    tma2d(sb + (10 + j) * SLOT, mx, fullb + (10 + j) * 8, j * 64, mt * 128);
                    mbar_expect_tx(fullb + j * 8, SLOT);
                    tma2d_mc(sb + j * SLOT + rank * 8192, mwq, fullb + j * 8, g * 512 + rank * 64, j * 64);
                }
                uint32_t so = 4, par = 1;
#pragma unroll 1
                for (int j = 4; j < 10; j++) {
                    mbar_wait(emptyb + so * 8, par);
                    mbar_expect_tx(fullb + so * 8, SLOT);
                    tma2d(sb + so * SLOT, mx, fullb + so * 8, j * 64, mt * 128);
                    so++;
                    mbar_wait(emptyb + so * 8, par);
                    mbar_expect_tx(fullb + so * 8, SLOT);
                    tma2d_mc(sb + so * SLOT + rank * 8192, mwq, fullb + so * 8, g * 512 + rank * 64, j * 64);
                    if (++so == NR) { so = 0; par ^= 1; }
                    if (j == 6) {
                        asm volatile("prefetch.tensormap [%0];" :: "l"(mk) : "memory");
                        asm volatile("prefetch.tensormap [%0];" :: "l"(mv) : "memory");
                        asm volatile("prefetch.tensormap [%0];" :: "l"(mwo) : "memory");
                        asm volatile("prefetch.tensormap [%0];" :: "l"(&prm.out) : "memory");
                    }
                }
                uint64_t pol;
                asm volatile("createpolicy.fractional.L2::evict_first.b64 %0, 1.0;" : "=l"(pol));
                int head = g * 4, j = 10;
#pragma unroll 1
                for (int u = 10; u < 46; u++) {
                    mbar_wait(emptyb + so * 8, par);
                    mbar_expect_tx(fullb + so * 8, SLOT);
                    if (j < 10) tma2d_mc(sb + so * SLOT + rank * 8192, mwq, fullb + so * 8, head * 128 + rank * 64, j * 64);
                    else tma3d(sb + so * SLOT, mk, fullb + so * 8, (j - 10) * 64, head * 32, mt * 4, pol);
                    if (++j == 12) { j = 0; head++; }
                    if (++so == NR) { so = 0; par ^= 1; }
                }
#pragma unroll 1
                for (int u = 46; u < 90; u++) {
                    if (u < 49) {
#pragma unroll 1
                        for (int i = u - 46; i < (u == 48 ? 4 : u - 45); i++) {
                            const uint32_t xs = 10 + i;
                            mbar_wait(emptyb + xs * 8, 0);
                            mbar_expect_tx(fullb + xs * 8, SLOT);
                            tma5d(sb + xs * SLOT, mv, fullb + xs * 8, (i & 1) * 64, 0, 0, (g * 4 + (i >> 1)) * 16, mt * 2, pol);
                        }
                    }
                    if (u == 54) {
                        mbar_wait(emptyb + 10 * 8, 1);
#pragma unroll 1
                        for (int i = 0; i < 2; i++) {
                            mbar_expect_tx(fullb + (10 + i) * 8, SLOT);
                            tma5d(sb + (10 + i) * SLOT, mv, fullb + (10 + i) * 8, i * 64, 0, 0, (g * 4 + 3) * 16, mt * 2, pol);
                        }
                    }
                    mbar_wait(emptyb + so * 8, par);
                    mbar_expect_tx(fullb + so * 8, SLOT);
                    if (u < 48) {
                        tma3d(sb + so * SLOT, mk, fullb + so * 8, (u - 46) * 64, head * 32, mt * 4, pol);
                    } else if (u < 50) {
                        tma5d(sb + so * SLOT, mv, fullb + so * 8, (u & 1) * 64, 0, 0, (g * 4 + 2) * 16, mt * 2, pol);
                    } else {
                        int ai = ((u - 50) >> 2) + g;
                        if (ai >= 10) ai -= 10;
                        tma2d_mc(sb + so * SLOT + rank * 8192, mwo, fullb + so * 8, ai * 64, (g * 4 + ((u - 50) & 3)) * 128 + rank * 64);
                    }
                    if (++so == NR) { so = 0; par ^= 1; }
                }
            }
        } else if (warp == 11) {
            const uint32_t zrow = fullb + 256;
            for (int i = lane; i < 80; i += 32) asm volatile("st.shared.v4.u32 [%0], {%1, %1, %1, %1};" :: "r"(zrow + i * 16), "r"(0u) : "memory");
            asm volatile("fence.proxy.async.shared::cta;" ::: "memory");
            __syncwarp();
            asm volatile("barrier.cluster.wait.aligned;" ::: "memory");
            if (lane == 0) {
                if (prm.zero_in_kernel) {
                    mbar_wait(gob, 0);
                    __nv_bfloat16* dst = prm.optr + (size_t)(mt * 128 + g * 16) * 1280 + p * 640;
#pragma unroll 1
                    for (int r = 0; r < 16; r++)
                        asm volatile("cp.async.bulk.global.shared::cta.bulk_group [%0], [%1], 1280;" :: "l"(dst + r * 1280), "r"(zrow) : "memory");
                    asm volatile("cp.async.bulk.commit_group;" ::: "memory");
                    asm volatile("cp.async.bulk.wait_group 0;" ::: "memory");
                    unsigned int old;
                    asm volatile("atom.acq_rel.gpu.global.add.u32 %0, [%1], 1;" : "=r"(old) : "l"(&g_zero_cnt[p * 8 + mt]) : "memory");
                    const unsigned int target = (old & ~7u) + 8u;
                    uint32_t it = 0; unsigned int cur = old + 1;
                    while ((int)(cur - target) < 0 && ++it < (1u << 23)) {
                        __nanosleep(200);
                        asm volatile("ld.acquire.gpu.global.u32 %0, [%1];" : "=r"(cur) : "l"(&g_zero_cnt[p * 8 + mt]) : "memory");
                    }
                    asm volatile("fence.proxy.async.global;" ::: "memory");
                }
                mbar_arrive_local(zerob);
            }
        } else {
            uint32_t tn = gtime32() + PF0 + (blockIdx.x * 37u % 128u) * PF_NS / 128u;
            auto pace = [&](uint32_t dt) { while ((int)(gtime32() - tn) < 0) {} tn += dt; };
            const size_t kvoff = ((size_t)(mt * 4) * 32 + g * 4) * 8192;
            if (warp == 9) {
                if (elect_one()) {
                    const char* kb = (const char*)prm.kptr[p] + kvoff;
                    const char* vb = (const char*)prm.vptr[p] + kvoff;
                    const CUtensorMap* mwq = &prm.wq[p];
                    { const uint32_t tl = gtime32() + LATE0; while ((int)(gtime32() - tl) < 0) {} }
                    if (mt < 4) pf2d(mwq, g * 512 + (mt & 1) * 64, (8 + (mt >> 1)) * 64);
                    if (g < 2) pf2d(&prm.x[p], (8 + g) * 64, mt * 128);
                    auto pfK = [&](const char* base) {
#pragma unroll 1
                        for (int b = 0; b < 4; b++) { pace(PF_NS); pf1d(base + (size_t)b * 262144, 8192); }
                    };
                    auto pfW = [&](int h) {
#pragma unroll 1
                        for (int q = mt; q < 24; q += 8) { pace(PF_NS * 5 / 6); if (q < 20) pf2d(mwq, (g * 4 + h) * 128 + (q & 1) * 64, (q >> 1) * 64); }
                    };
                    auto pfWo = [&](int a) { pace(PF_NS); pf2d(&prm.wo[p], (g + a < 10 ? g + a : g + a - 10) * 64, g * 512 + mt * 64); };
                    tn += 4 * PF_NS;
                    pfW(1); pfK(kb + 8192); pfW(2);
                    tn += 4 * PF_NS;
                    pfK(kb + 2 * 8192); pfW(3);
                    tn += 4 * PF_NS;
                    pfK(kb + 3 * 8192);
                    pfK(vb + 2 * 8192);
                    pfWo(0);
                    pfK(vb + 3 * 8192);
                    pfWo(1); pfWo(2);
                }
                __syncwarp();
            } else {
                uint32_t v[8];
                const char* kb = (const char*)prm.kptr[p] + kvoff + lane * 256;
#pragma unroll
                for (int i = 0; i < 4; i++) { pace(PF_NS); v[i] = ld_pf256(kb + (size_t)i * 262144); }
                uint32_t sink = v[0] ^ v[1] ^ v[2] ^ v[3];
                tn += 4 * PF_NS + 6 * (PF_NS * 5 / 6);
                const char* vb = (const char*)prm.vptr[p] + kvoff + lane * 128;
#pragma unroll 1
                for (int h = 0; h < 2; h++) {
#pragma unroll
                    for (int i = 0; i < 8; i++) { pace(PF_NS / 2); v[i] = ld_pf128(vb + (size_t)(i >> 1) * 262144 + (i & 1) * 4096); }
#pragma unroll
                    for (int i = 0; i < 8; i++) sink ^= v[i];
                    vb += 8192;
                    tn += 4 * PF_NS + 3 * (PF_NS * 5 / 6);
                }
                if (sink == 0x9e3779b9u) g_sink = sink;
            }
            asm volatile("barrier.cluster.wait.aligned;" ::: "memory");
        }
    } else {
        asm volatile("setmaxnreg.inc.sync.aligned.u32 240;");
        asm volatile("barrier.cluster.wait.aligned;" ::: "memory");
        const int wg = warp >> 2, wq4 = warp & 3;
        const bool sig = (wq4 < 2) && lane == 0;
        const uint32_t rempty = mapa(emptyb, wq4 & 1);
        const bool lower = wq4 < 2;
        const uint32_t meta = lower ? 0x44444444u : 0xEEEEEEEEu;
        const uint32_t dK = mkdesc(sb + wg * 8192, 16);
        const uint32_t dW = mkdesc(sb, 8192);
        const uint32_t dV = mkdesc(sb + wg * 8192, SLOT);
        const uint32_t frag_off = (uint32_t)(wg * 8192 + wq4 * 2048 + ((lane & 7) + ((lane >> 3) & 1) * 8) * 128);
        const int schunk = lane >> 4, sx = lane & 7;
        uint32_t cs = 0, cp = 0;
        uint32_t ps;
        uint32_t hb = 0;
        auto advance = [&]() { ps = cs; if (++cs == NR) { cs = 0; cp ^= 1; } };
        uint32_t xr[6][16];
        uint32_t P0[8], P1[8], P2[8];
        float q[64], e[16];
        auto softmaxA = [&](float (&e)[16]) {
            float m0 = fmaxf(fmaxf(fmaxf(e[0], e[1]), fmaxf(e[4], e[5])), fmaxf(fmaxf(e[8], e[9]), fmaxf(e[12], e[13])));
            float m1 = fmaxf(fmaxf(fmaxf(e[2], e[3]), fmaxf(e[6], e[7])), fmaxf(fmaxf(e[10], e[11]), fmaxf(e[14], e[15])));
            m0 = fmaxf(m0, __shfl_xor_sync(0xffffffffu, m0, 1)); m1 = fmaxf(m1, __shfl_xor_sync(0xffffffffu, m1, 1));
            m0 = fmaxf(m0, __shfl_xor_sync(0xffffffffu, m0, 2)); m1 = fmaxf(m1, __shfl_xor_sync(0xffffffffu, m1, 2));
            const float c = 0.08838834764831845f * 1.4426950408889634f;
            const float b0 = -m0 * c, b1 = -m1 * c;
#pragma unroll
            for (int j = 0; j < 4; j++) {
                e[4 * j] = ex2(fmaf(e[4 * j], c, b0)); e[4 * j + 1] = ex2(fmaf(e[4 * j + 1], c, b0));
                e[4 * j + 2] = ex2(fmaf(e[4 * j + 2], c, b1)); e[4 * j + 3] = ex2(fmaf(e[4 * j + 3], c, b1));
            }
        };
        auto softmaxB = [&](float (&e)[16], uint32_t (&P)[8]) {
            float s0 = ((e[0] + e[1]) + (e[4] + e[5])) + ((e[8] + e[9]) + (e[12] + e[13]));
            float s1 = ((e[2] + e[3]) + (e[6] + e[7])) + ((e[10] + e[11]) + (e[14] + e[15]));
            s0 += __shfl_xor_sync(0xffffffffu, s0, 1); s1 += __shfl_xor_sync(0xffffffffu, s1, 1);
            s0 += __shfl_xor_sync(0xffffffffu, s0, 2); s1 += __shfl_xor_sync(0xffffffffu, s1, 2);
            float r0, r1;
            asm("rcp.approx.ftz.f32 %0, %1;" : "=f"(r0) : "f"(s0));
            asm("rcp.approx.ftz.f32 %0, %1;" : "=f"(r1) : "f"(s1));
#pragma unroll
            for (int j = 0; j < 4; j++) {
                P[2 * j] = pack_bf16(e[4 * j] * r0, e[4 * j + 1] * r0);
                P[2 * j + 1] = pack_bf16(e[4 * j + 2] * r1, e[4 * j + 3] * r1);
            }
        };
        auto qtile = [&](int kt, bool wait = true, bool hand = true) {
            if (wait) mbar_wait(fullb + cs * 8, cp);
            const uint32_t db = dW + cs * SD;
            if (kt == 9 && hand && wg == 1) asm volatile("bar.sync %0, 256;" :: "r"(1 + (hb & 3)) : "memory");
            WG_FENCE();
            if (kt >= 4) {
                const int xi = kt >= 4 ? kt - 4 : 0;
#pragma unroll
                for (int kk = 0; kk < 4; kk++)
                    wgmma_n128_rs_t1(q, xr[xi][4 * kk], xr[xi][4 * kk + 1], xr[xi][4 * kk + 2], xr[xi][4 * kk + 3], db + kk * 128, true);
            } else {
#pragma unroll
                for (int kk = 0; kk < 4; kk++) wgmma_n128_ss_t1(q, dK + (kt + 10) * SD + kk * 2, db + kk * 128, (kt | kk) != 0);
            }
            WG_COMMIT();
            if (kt == 9 && hand) { if (wg == 0) asm volatile("bar.arrive %0, 256;" :: "r"(1 + (hb & 3)) : "memory"); hb++; }
        };
#pragma unroll
        for (int kt = 0; kt < 10; kt++) {
            if (kt < 4) {
                mbar_wait(fullb + (10 + kt) * 8, 0);
            } else {
                const int xs = (2 * kt - 4) % NR, xi = kt >= 4 ? kt - 4 : 0;
                mbar_wait(fullb + xs * 8, (2 * kt - 4) / NR);
#pragma unroll
                for (int kk = 0; kk < 4; kk++)
                    ldsm4(sb + xs * SLOT + frag_off + (((2 * kk + schunk) ^ sx) << 4), xr[xi][4 * kk], xr[xi][4 * kk + 1], xr[xi][4 * kk + 2], xr[xi][4 * kk + 3]);
                cs = xs + 1; cp = (2 * kt - 4) / NR;
            }
            qtile(kt);
            if (kt > 0) {
                WG_WAIT(1);
                if (sig) { if (kt > 4) mbar_arrive_cluster(rempty + (ps - 1) * 8); mbar_arrive_cluster(rempty + ps * 8); }
            }
            advance();
        }
        auto cvtQ = [&]() {
            pin(q);
#pragma unroll
            for (int i = 31; i >= 0; i--) q[32 + i] = __uint_as_float(pack_bf16(q[2 * i], q[2 * i + 1]));
        };
        auto issueS = [&](uint32_t slot) {
            const uint32_t dk = dK + slot * SD;
            WG_FENCE();
#pragma unroll
            for (int kk = 0; kk < 8; kk++)
                wgmma_n64_rs_t0(q, __float_as_uint(q[32 + 4 * kk]), __float_as_uint(q[33 + 4 * kk]), __float_as_uint(q[34 + 4 * kk]), __float_as_uint(q[35 + 4 * kk]),
                                dk + (kk >> 2) * SD + (kk & 3) * 2, kk != 0);
            WG_COMMIT();
        };
        auto takeS = [&](uint32_t slot) {
            pin(q);
            if (sig) { mbar_arrive_cluster(rempty + slot * 8); mbar_arrive_cluster(rempty + slot * 8 + 8); }
#pragma unroll
            for (int i = 0; i < 16; i++) e[i] = lower ? q[i] : q[16 + i];
            pin(e);
        };
        WG_WAIT(0);
        if (sig) mbar_arrive_cluster(rempty + (ps - 1) * 8);
#pragma unroll 1
        for (int h = 0; h < 3; h++) {
            if (h > 0) {
#pragma unroll
                for (int kt = 8; kt < 10; kt++) {
                    qtile(kt);
                    WG_WAIT(1);
                    if (sig) mbar_arrive_cluster(rempty + ps * 8);
                    advance();
                }
            }
            WG_WAIT(0);
            if (sig) mbar_arrive_cluster(rempty + ps * 8);
            cvtQ();
            mbar_wait(fullb + cs * 8, cp); mbar_wait(fullb + cs * 8 + 8, cp);
            issueS(cs);
            const uint32_t ks = cs;
            advance(); advance();
            WG_WAIT(0);
            takeS(ks);
            qtile(0); advance();
            qtile(1);
#pragma unroll
            for (int i = 0; i < 8; i++) { P0[i] = P1[i]; P1[i] = P2[i]; }
            softmaxA(e); softmaxB(e, P2);
            const bool relx = h == 2 && wq4 == 2 && lane == 0;
            WG_WAIT(1);
            if (sig) mbar_arrive_cluster(rempty + ps * 8);
            if (relx) mbar_arrive_local(emptyb + 10 * 8);
            advance();
#pragma unroll
            for (int kt = 2; kt < 8; kt++) {
                qtile(kt);
                WG_WAIT(1);
                if (sig) mbar_arrive_cluster(rempty + ps * 8);
                if (kt < 5 && relx) mbar_arrive_local(emptyb + (9 + kt) * 8);
                advance();
            }
        }
        uint32_t O[4][32];
        float acc[32];
        uint32_t pk[16];
        const uint32_t dO = mkdesc(sb, 16);
        const uint32_t stg = sb + 10 * SLOT + wg * 8192 + wq4 * 2048;
        uint32_t lane2 = 0;
        const int orow = mt * 128 + wg * 64 + wq4 * 16;
        auto oproj2 = [&](int h, uint32_t s0, uint32_t s1) {
            const uint32_t d0 = dO + s0 * SD, d1 = dO + s1 * SD;
            WG_FENCE();
#pragma unroll
            for (int kk = 0; kk < 8; kk++) wgmma_n64_rs_t1(acc, O[h][4 * kk], O[h][4 * kk + 1], O[h][4 * kk + 2], O[h][4 * kk + 3], d0 + kk * 128, (h | kk) != 0);
#pragma unroll
            for (int kk = 0; kk < 8; kk++) wgmma_n64_rs_t1(acc, O[h + 1][4 * kk], O[h + 1][4 * kk + 1], O[h + 1][4 * kk + 2], O[h + 1][4 * kk + 3], d1 + kk * 128, true);
            WG_COMMIT();
        };
        auto oproj1 = [&](int h, uint32_t s0) {
            const uint32_t d0 = dO + s0 * SD;
            WG_FENCE();
#pragma unroll
            for (int kk = 0; kk < 8; kk++) wgmma_n64_rs_t1(acc, O[h][4 * kk], O[h][4 * kk + 1], O[h][4 * kk + 2], O[h][4 * kk + 3], d0 + kk * 128, (h | kk) != 0);
            WG_COMMIT();
        };
        auto pv = [&](float (&o)[64], uint32_t (&P)[8], int vs) {
            WG_FENCE();
            wgmma_n128_sp_t1(o, P[0], P[1], P[2], P[3], dV + vs * SD, meta, false);
            wgmma_n128_sp_t1(o, P[4], P[5], P[6], P[7], dV + vs * SD + 256, meta, true);
            WG_COMMIT();
        };
        auto fb = [&](uint32_t slot) { return fullb + slot * 8; };
        auto rel = [&](uint32_t slot) { if (sig) mbar_arrive_cluster(rempty + slot * 8); };
        auto cvtO = [&](float (&o)[64], int h) {
            pin(o);
#pragma unroll
            for (int i = 0; i < 32; i++) O[h][i] = pack_bf16(o[2 * i], o[2 * i + 1]);
        };
        auto col = [&](int ai) { ai += g; if (ai >= 10) ai -= 10; return p * 640 + ai * 64; };
        auto enter = [&](bool first) { if (!(first && wg == 0)) asm volatile("bar.sync %0, 256;" :: "r"(6 + wg) : "memory"); };
        auto leave = [&](bool last) { if (!(last && wg == 1)) asm volatile("bar.arrive %0, 256;" :: "r"(7 - wg) : "memory"); };
        {
            float o[64];
            mbar_wait4(fb(0), 1, fb(1), 1, fb(10), 1, fb(11), 1);
            WG_WAIT(0);
            rel(9);
            cs = 0;
            enter(true);
            pv(o, P0, 10);
            qtile(8, false);
            WG_WAIT(1);
            if (wq4 == 2 && lane == 0) mbar_arrive_local(emptyb + 10 * 8);
            cvtO(o, 0);
            cs = 1;
            qtile(9, false, false);
            leave(false);
            WG_WAIT(0);
            rel(0); rel(1);
            cvtQ();
            mbar_wait4(fb(2), 1, fb(3), 1, fb(12), 1, fb(13), 1);
            enter(false);
            pv(o, P1, 12);
            issueS(2);
            leave(false);
            WG_WAIT(1);
            cvtO(o, 1);
            WG_WAIT(0);
            takeS(2);
            mbar_wait4(fb(4), 1, fb(5), 1, fb(6), 1, fb(6), 1);
            enter(false);
            pv(o, P2, 4);
            oproj1(0, 6);
            leave(false);
            sched_fence(); pin(e);
            WG_WAIT(1);
            rel(4); rel(5);
            cvtO(o, 2);
            softmaxA(e);
            pin(e);
            mbar_wait2(fb(7), 1, fb(8), 1);
            enter(false);
            oproj2(1, 7, 8);
            leave(false);
            sched_fence(); pin(e);
            softmaxB(e, P0);
            asm volatile("mov.u32 %0, %%laneid;" : "=r"(lane2));
            mbar_wait4(fb(10), 0, fb(11), 0, fb(9), 1, fb(9), 1);
            enter(false);
            pv(o, P0, 10);
            leave(false);
            WG_WAIT(0);
            rel(6); rel(7);
            if (tid == 96) mbar_arrive_local(gob);
            cvtO(o, 3);
            sched_fence();
            enter(false);
            oproj1(3, 9);
            leave(false);
        }
        ps = 8; cs = 0; cp = 0;
        auto advance2 = [&]() { ps = cs; cs += 2; if (cs == NR) { cs = 0; cp ^= 1; } };
#pragma unroll 1
        for (int st = 0; st < 10; st++) {
            if (st < 9) mbar_wait2(fb(cs), cp, fb(cs) + 8, cp);
            WG_WAIT(0);
            if (st < 7) { rel(ps); rel(ps + 1); }
            pin(acc);
#pragma unroll
            for (int i = 0; i < 16; i++) pk[i] = pack_bf16(acc[2 * i], acc[2 * i + 1]);
            if (st < 9) { enter(false); oproj2(0, cs, cs + 1); leave(false); advance2(); }
            asm volatile("cp.async.bulk.wait_group.read 2;" ::: "memory");
            __syncwarp();
            const uint32_t bo = (uint32_t)(st & 3) * SLOT;
#pragma unroll
            for (int c = 0; c < 8; c += 2)
                stsm4(stg + (lane2 & 15) * 128 + bo + (((c + (lane2 >> 4)) ^ (lane2 & 7)) << 4), pk[2 * c], pk[2 * c + 1], pk[2 * c + 2], pk[2 * c + 3]);
            asm volatile("fence.proxy.async.shared::cta;" ::: "memory");
            __syncwarp();
            if (st == 2) tma_red2d_commit(lane2 == 0, &prm.out, stg + SLOT, col(1), orow);
            if (st < 9) {
                mbar_wait2(fb(cs), cp, fb(cs) + 8, cp);
                WG_WAIT(0);
                if (st < 7) { rel(ps); rel(ps + 1); }
                enter(false);
                oproj2(2, cs, cs + 1);
                leave(st == 8);
                advance2();
            }
            const int rt = st == 1 ? 0 : st;
            if (st == 1) mbar_wait(zerob, 0);
            tma_red2d_commit(lane2 == 0 && st >= 1, &prm.out, stg + (rt & 3) * SLOT, col(rt), orow);
        }
        WG_WAIT(0);
        asm volatile("cp.async.bulk.wait_group.read 0;" ::: "memory");
    }
}

typedef CUresult (*EncodeTiledFn)(CUtensorMap*, CUtensorMapDataType, cuuint32_t, void*, const cuuint64_t*, const cuuint64_t*,
                                  const cuuint32_t*, const cuuint32_t*, CUtensorMapInterleave, CUtensorMapSwizzle,
                                  CUtensorMapL2promotion, CUtensorMapFloatOOBfill);

void encode(EncodeTiledFn fn, CUtensorMap* m, const void* ptr, int rank, const cuuint64_t* dims, const cuuint64_t* strides, const cuuint32_t* box) {
    cuuint32_t es[5] = {1, 1, 1, 1, 1};
    fn(m, CU_TENSOR_MAP_DATA_TYPE_BFLOAT16, (cuuint32_t)rank, const_cast<void*>(ptr), dims, strides, box, es,
       CU_TENSOR_MAP_INTERLEAVE_NONE, CU_TENSOR_MAP_SWIZZLE_128B, CU_TENSOR_MAP_L2_PROMOTION_L2_128B, CU_TENSOR_MAP_FLOAT_OOB_FILL_NONE);
}

}

extern "C" void kernel_launch(void* const* d_in, const int* in_sizes, int n_in, void* d_out, int out_size) {
    (void)in_sizes; (void)n_in;
    static EncodeTiledFn fn = nullptr;
    static int coresident = 0;
    if (!fn) {
        void* f = nullptr; cudaDriverEntryPointQueryResult qr;
        cudaGetDriverEntryPoint("cuTensorMapEncodeTiled", &f, cudaEnableDefault, &qr);
        fn = (EncodeTiledFn)f;
        cudaFuncSetAttribute(fused_kernel, cudaFuncAttributeMaxDynamicSharedMemorySize, SMEM_BYTES);
        cudaLaunchConfig_t cfg = {};
        cfg.gridDim = dim3(128); cfg.blockDim = dim3(384); cfg.dynamicSmemBytes = SMEM_BYTES;
        cudaLaunchAttribute at[1];
        at[0].id = cudaLaunchAttributeClusterDimension; at[0].val.clusterDim.x = 2; at[0].val.clusterDim.y = 1; at[0].val.clusterDim.z = 1;
        cfg.attrs = at; cfg.numAttrs = 1;
        int nc = 0;
        if (cudaOccupancyMaxActiveClusters(&nc, fused_kernel, &cfg) == cudaSuccess && nc >= 64) coresident = 1;
        (void)cudaGetLastError();
    }
    Params prm;
    for (int p = 0; p < 2; p++) {
        const void* x = d_in[p * 5 + 0]; const void* k = d_in[p * 5 + 1]; const void* v = d_in[p * 5 + 2];
        const void* wq = d_in[p * 5 + 3]; const void* wo = d_in[p * 5 + 4];
        { cuuint64_t d[2] = {640, 1024}; cuuint64_t s[1] = {1280}; cuuint32_t b[2] = {64, 128}; encode(fn, &prm.x[p], x, 2, d, s, b); }
        { cuuint64_t d[2] = {4096, 640}; cuuint64_t s[1] = {8192}; cuuint32_t b[2] = {64, 64}; encode(fn, &prm.wq[p], wq, 2, d, s, b); }
        { cuuint64_t d[3] = {128, 1024, 32}; cuuint64_t s[2] = {256, 262144}; cuuint32_t b[3] = {64, 32, 4}; encode(fn, &prm.k[p], k, 3, d, s, b); }
        { cuuint64_t d[5] = {128, 2, 2, 512, 16}; cuuint64_t s[4] = {256, 262144, 512, 524288}; cuuint32_t b[5] = {64, 2, 2, 16, 2};
          encode(fn, &prm.v[p], v, 5, d, s, b); }
        { cuuint64_t d[2] = {640, 4096}; cuuint64_t s[1] = {1280}; cuuint32_t b[2] = {64, 64}; encode(fn, &prm.wo[p], wo, 2, d, s, b); }
        prm.kptr[p] = (const __nv_bfloat16*)k; prm.vptr[p] = (const __nv_bfloat16*)v;
        prm.xw[p] = (const __nv_bfloat16*)x; prm.xw[2 + p] = (const __nv_bfloat16*)wq;
    }
    { cuuint64_t d[2] = {1280, 1024}; cuuint64_t s[1] = {2560}; cuuint32_t b[2] = {64, 16}; encode(fn, &prm.out, d_out, 2, d, s, b); }
    prm.optr = (__nv_bfloat16*)d_out;
    prm.zero_in_kernel = coresident;
    if (!coresident) cudaMemsetAsync(d_out, 0, (size_t)out_size * sizeof(__nv_bfloat16), cudaStreamPerThread);
    fused_kernel<<<128, 384, SMEM_BYTES, cudaStreamPerThread>>>(prm);
}
```
